```python
import torch

def _softmax(x, axis=-1):
    return torch.softmax(x, dim=axis)
def _gelu(x):
    return torch.nn.functional.gelu(x, approximate="tanh")
def _silu(x):
    return torch.nn.functional.silu(x)
def _sigmoid(x):
    return torch.sigmoid(x)
def _layernorm(x, axis=-1, eps=1e-5):
    m = x.mean(dim=axis, keepdim=True)
    v = x.var(dim=axis, keepdim=True, unbiased=False)
    return (x - m) / torch.sqrt(v + eps)
def _scatter_add(tgt, idx, src, axis=0):
    return tgt.clone().index_add_(axis, idx, src)
def _segment_sum(src, seg, n):
    out = torch.zeros((n,) + src.shape[1:], dtype=src.dtype)
    return out.index_add_(0, seg, src)
def _pad(x, pw):
    flat = tuple(v for pair in reversed(pw) for v in pair)
    return torch.nn.functional.pad(x, flat)

kernel_name = 'parallel_sum__sliding_block_cached__mixer_channel_mlp__decode'

def setup_inputs():

    _w = (lambda a: (lambda t: t.to(torch.bfloat16) if t.is_floating_point() else t)(torch.as_tensor(a)))
    def _A_setup():
        B, Sq, D = 1, 1, 576
        Hq, Hkv, Sk, Dh = 32, 16, 16384, 128
        assert Hq % Hkv == 0, (Hq, Hkv)
        return {
            "x": _w((lambda *s: torch.randn(*s, dtype=torch.bfloat16) * 0.05)(B, Sq, D)),
            "k_cache": _w((lambda *s: torch.randn(*s, dtype=torch.bfloat16) * 3.2)(B, Hkv, Sk, Dh)),
            "v_cache": _w((lambda *s: torch.randn(*s, dtype=torch.bfloat16) * 0.4)(B, Hkv, Sk, Dh)),
            "wq": _w((lambda *s: torch.randn(*s, dtype=torch.bfloat16) * 3.2)(D, Hq * Dh) * (D ** -0.5)),
            "wo": _w((lambda *s: torch.randn(*s, dtype=torch.bfloat16) * 0.4)(Hq * Dh, D) * ((Hq * Dh) ** -0.5)),
        }
    _A_in = _A_setup()

    def _B_setup():
        B, S, D, F = 1, 1, 576, 4608
        return {
            "x": _w((lambda *s: torch.randn(*s, dtype=torch.bfloat16) * 0.05)(B, S, D)),
            "w1": _w((lambda *s: torch.randn(*s, dtype=torch.bfloat16) * 3.2)(D, F) * (D ** -0.5)),
            "b1": _w((lambda *s: torch.randn(*s, dtype=torch.bfloat16) * 1.6)(F)),
            "w2": _w((lambda *s: torch.randn(*s, dtype=torch.bfloat16) * 0.1)(F, D) * (F ** -0.5)),
            "b2": _w((lambda *s: torch.randn(*s, dtype=torch.bfloat16) * 0.1)(D)),
        }
    _B_in = _B_setup()

    return {
        "A_x": _A_in["x"],
        "A_k_cache": _A_in["k_cache"],
        "A_v_cache": _A_in["v_cache"],
        "A_wq": _A_in["wq"],
        "A_wo": _A_in["wo"],
        "B_x": _B_in["x"],
        "B_w1": _B_in["w1"],
        "B_b1": _B_in["b1"],
        "B_w2": _B_in["w2"],
        "B_b2": _B_in["b2"],
    }

def reference(A_x, A_k_cache, A_v_cache, A_wq, A_wo, B_x, B_w1, B_b1, B_w2, B_b2):
    def _A_ref(x, k_cache, v_cache, wq, wo):
        B, Sq, D = x.shape
        Hq, Dh = 32, 128
        Hkv, Sk = k_cache.shape[1], k_cache.shape[2]
        W = min(4096, max(256, Sk // 4))
        rep = Hq // Hkv
        q = (lambda x, *d: x.permute(*d))((x @ wq).reshape(B, Sq, Hq, Dh), 0, 2, 1, 3)
        k = (lambda x, n, axis: torch.repeat_interleave(x, n, dim=axis))(k_cache[:, :, Sk - W:, :], rep, axis=1)
        v = (lambda x, n, axis: torch.repeat_interleave(x, n, dim=axis))(v_cache[:, :, Sk - W:, :], rep, axis=1)
        scores = torch.einsum("bhqd,bhkd->bhqk", q, k) * (Dh ** -0.5)
        p = _softmax(scores, axis=-1)
        o = torch.einsum("bhqk,bhkd->bhqd", p, v)
        return (lambda x, *d: x.permute(*d))(o, 0, 2, 1, 3).reshape(B, Sq, Hq * Dh) @ wo

    def _B_ref(x, w1, b1, w2, b2):
        y = _layernorm(x, axis=-1)
        h = _gelu(torch.einsum("bsd,df->bsf", y, w1) + b1)
        return torch.einsum("bsf,fd->bsd", h, w2) + b2

    x = A_x
    xn = _layernorm(x, axis=-1)
    return x + _A_ref(xn, A_k_cache, A_v_cache, A_wq, A_wo) + _B_ref(xn, B_w1, B_b1, B_w2, B_b2)
```

```cpp
#include <cuda_runtime.h>
#include <cuda_bf16.h>
#include <cuda.h>
#include <stdint.h>

namespace {

constexpr int D_ = 576, HKV = 16, SK = 16384, DH = 128, WIN = 4096, FF = 4608, QC = 4096;
constexpr int NATT = 128, NCTA = 132, NTHREADS = 320, NFIN = 72;
constexpr int CHUNK = 16384, NCH = 8;
constexpr int TSLOT = 16 * D_ * 2;
constexpr int HBOX = 192 * 64;
#define DEPTH_A 4
#define DEPTH_B 4
#define DEPTH_C 4
#define SWITCH_AB 6
#define PACE_PS 43000
#define PACE_LEAD 1600
#define DEPTH_H 3
#define NINIT 1
#define QDELAY 0
constexpr int OP_V = 8, OP_H = 16, OP_W = 19, NOPS = 23;
constexpr int SPIN_LIMIT = 1 << 22;

constexpr int SM_KV = 0;
constexpr int SM_T = NCH * CHUNK;
constexpr int SM_RED = SM_T + 4 * TSLOT;
constexpr int SM_HRED = SM_RED + 8 * 256 * 4;
constexpr int SM_XN = SM_HRED + 4 * 8 * 32 * 4;
constexpr int SM_Y = SM_XN + D_ * 2;
constexpr int SM_B1 = SM_Y + D_ * 2;
constexpr int SM_QS = SM_B1 + 256;
constexpr int SM_HS = SM_QS + 512;
constexpr int SM_WMAX = SM_HS + 256;
constexpr int SM_WSUM = SM_WMAX + 64;
constexpr int SM_TAG = SM_WSUM + 64;
constexpr int SM_BAR = SM_TAG + 16;
constexpr int SM_TOTAL = SM_BAR + (NOPS + 12) * 8;

struct __align__(128) Scratch {
    unsigned epoch[32];
    unsigned qx[NATT * 256];
    unsigned ox[NATT * 8 * 32];
    unsigned ml[NATT * 8];
    unsigned part[NFIN * NCTA * 8];
};
__device__ Scratch g_scratch;

#define PROFD(cond, slot, dep) do { } while (0)
#define PROF(cond, slot) do { } while (0)

__device__ __forceinline__ void mbar_init(unsigned bar, unsigned cnt) {
    asm volatile("mbarrier.init.shared::cta.b64 [%0], %1;" ::"r"(bar), "r"(cnt) : "memory");
}
__device__ __forceinline__ void mbar_expect_tx(unsigned bar, unsigned bytes) {
    asm volatile("mbarrier.arrive.expect_tx.shared::cta.b64 _, [%0], %1;" ::"r"(bar), "r"(bytes) : "memory");
}
__device__ __forceinline__ void mbar_arrive(unsigned bar) {
    asm volatile("mbarrier.arrive.shared::cta.b64 _, [%0];" ::"r"(bar) : "memory");
}
__device__ __forceinline__ void mbar_wait(unsigned bar) {
    unsigned ok;
    int it = 0;
    do {
        asm volatile(
            "{ .reg .pred p; mbarrier.try_wait.parity.shared::cta.b64 p, [%1], 0; selp.u32 %0, 1, 0, p; }"
            : "=r"(ok) : "r"(bar) : "memory");
    } while (!ok && ++it < SPIN_LIMIT);
}
__device__ __forceinline__ void bulk_load(unsigned dst, const void* src, unsigned bytes, unsigned bar) {
    asm volatile("cp.async.bulk.shared::cluster.global.mbarrier::complete_tx::bytes [%0], [%1], %2, [%3];"
                 ::"r"(dst), "l"(src), "r"(bytes), "r"(bar) : "memory");
}
__device__ __forceinline__ uint4 ldg_stream(const void* p) {
    uint4 v;
    asm volatile("ld.global.nc.L1::no_allocate.v4.u32 {%0,%1,%2,%3}, [%4];"
                 : "=r"(v.x), "=r"(v.y), "=r"(v.z), "=r"(v.w) : "l"(p));
    return v;
}
__device__ __forceinline__ unsigned ld_rlx(const unsigned* p) {
    unsigned v;
    asm volatile("ld.relaxed.gpu.global.u32 %0, [%1];" : "=r"(v) : "l"(p) : "memory");
    return v;
}
__device__ __forceinline__ uint2 ld_rlx2(const unsigned* p) {
    uint2 v;
    asm volatile("ld.relaxed.gpu.global.v2.u32 {%0,%1}, [%2];" : "=r"(v.x), "=r"(v.y) : "l"(p) : "memory");
    return v;
}
__device__ __forceinline__ uint4 ld_rlx4(const unsigned* p) {
    uint4 v;
    asm volatile("ld.relaxed.gpu.global.v4.u32 {%0,%1,%2,%3}, [%4];"
                 : "=r"(v.x), "=r"(v.y), "=r"(v.z), "=r"(v.w) : "l"(p) : "memory");
    return v;
}
__device__ __forceinline__ void st_rlx(unsigned* p, unsigned v) {
    asm volatile("st.relaxed.gpu.global.u32 [%0], %1;" ::"l"(p), "r"(v) : "memory");
}
__device__ __forceinline__ uint4 lds128(unsigned a) {
    uint4 v;
    asm volatile("ld.shared.v4.u32 {%0,%1,%2,%3}, [%4];" : "=r"(v.x), "=r"(v.y), "=r"(v.z), "=r"(v.w) : "r"(a));
    return v;
}
__device__ __forceinline__ void bar_sync(int id, int n) { asm volatile("bar.sync %0, %1;" ::"r"(id), "r"(n) : "memory"); }
__device__ __forceinline__ void bar_arrive(int id, int n) { asm volatile("bar.arrive %0, %1;" ::"r"(id), "r"(n) : "memory"); }
__device__ __forceinline__ void mma16816(float (&c)[4], unsigned a0, unsigned a1, unsigned a2, unsigned a3,
                                         unsigned b0, unsigned b1) {
    asm volatile(
        "mma.sync.aligned.m16n8k16.row.col.f32.bf16.bf16.f32 {%0,%1,%2,%3}, {%4,%5,%6,%7}, {%8,%9}, {%0,%1,%2,%3};"
        : "+f"(c[0]), "+f"(c[1]), "+f"(c[2]), "+f"(c[3])
        : "r"(a0), "r"(a1), "r"(a2), "r"(a3), "r"(b0), "r"(b1));
}
__device__ __forceinline__ void ldsm4t(unsigned (&r)[4], unsigned a) {
    asm volatile("ldmatrix.sync.aligned.m8n8.x4.trans.shared.b16 {%0,%1,%2,%3}, [%4];"
                 : "=r"(r[0]), "=r"(r[1]), "=r"(r[2]), "=r"(r[3]) : "r"(a));
}
__device__ __forceinline__ float bfr(float v) { return __bfloat162float(__float2bfloat16_rn(v)); }
__device__ __forceinline__ float bf_lo(unsigned w) { return __uint_as_float(w << 16); }
__device__ __forceinline__ float bf_hi(unsigned w) { return __uint_as_float(w & 0xffff0000u); }
__device__ __forceinline__ unsigned pack_bf(float lo, float hi) {
    __nv_bfloat162 v = __floats2bfloat162_rn(lo, hi);
    return *reinterpret_cast<unsigned*>(&v);
}
__device__ __forceinline__ float warp_sum(float v) {
#pragma unroll
    for (int o = 16; o; o >>= 1) v += __shfl_xor_sync(0xffffffffu, v, o);
    return v;
}
__device__ __forceinline__ unsigned tagf(float v, unsigned tag) { return (__float_as_uint(v) & ~3u) | tag; }
__device__ __forceinline__ float untag(unsigned w) { return __uint_as_float(w & ~3u); }

__device__ __forceinline__ void tma_2d(unsigned dst, const CUtensorMap* map, int c0, int c1, unsigned bar) {
    asm volatile(
        "cp.async.bulk.tensor.2d.shared::cluster.global.mbarrier::complete_tx::bytes [%0], [%1, {%3, %4}], [%2];"
        ::"r"(dst), "l"(map), "r"(bar), "r"(c0), "r"(c1) : "memory");
}
__device__ __forceinline__ unsigned gtime32() {
    unsigned c;
    asm volatile("mov.u32 %0, %globaltimer_lo;" : "=r"(c));
    return c;
}
__device__ __forceinline__ unsigned clock32() {
    unsigned c;
    asm volatile("mov.u32 %0, %clock;" : "=r"(c));
    return c;
}
__device__ __forceinline__ unsigned lds32(unsigned a) {
    unsigned v;
    asm volatile("ld.shared.u32 %0, [%1];" : "=r"(v) : "r"(a));
    return v;
}

__device__ __forceinline__ void layernorm18(unsigned (&w)[9]) {
    float s0 = 0.f, s1 = 0.f, s2 = 0.f;
#pragma unroll
    for (int i = 0; i < 3; i++) {
        s0 += bf_lo(w[i]) + bf_hi(w[i]);
        s1 += bf_lo(w[i + 3]) + bf_hi(w[i + 3]);
        s2 += bf_lo(w[i + 6]) + bf_hi(w[i + 6]);
    }
    const float mean = warp_sum(s0 + s1 + s2) * (1.0f / D_);
    float q0 = 0.f, q1 = 0.f;
#pragma unroll
    for (int i = 0; i < 9; i++) {
        const float a = bf_lo(w[i]) - mean, c = bf_hi(w[i]) - mean;
        q0 = fmaf(a, a, q0);
        q1 = fmaf(c, c, q1);
    }
    const float var = bfr(warp_sum(q0 + q1) * (1.0f / D_));
    const float m = bfr(mean);
    float sq, rs;
    asm("sqrt.approx.f32 %0, %1;" : "=f"(sq) : "f"(bfr(var + 1e-5f)));
    asm("rcp.approx.f32 %0, %1;" : "=f"(rs) : "f"(bfr(sq)));
#pragma unroll
    for (int i = 0; i < 9; i++) {
        const unsigned d = pack_bf(bf_lo(w[i]) - m, bf_hi(w[i]) - m);
        w[i] = pack_bf(bf_lo(d) * rs, bf_hi(d) * rs);
    }
}
__device__ __forceinline__ float gelu_tanh(float x) {
    const float k0 = 0.7978845608028654f, k1 = 0.044715f;
    float inner = k0 * (x + k1 * x * x * x);
    return 0.5f * x * (1.0f + tanhf(inner));
}

__device__ __forceinline__ float gather_piece(const unsigned* p, bool need, unsigned tag, int lane) {
    uint4 v = make_uint4(0u, 0u, 0u, 0u);
    int it = 0;
    do {
        if (need) {
            v = ld_rlx4(p);
            need = (((v.x ^ tag) | (v.y ^ tag) | (v.z ^ tag) | (v.w ^ tag)) & 3u) != 0;
        }
    } while (__any_sync(0xffffffffu, need) && ++it < SPIN_LIMIT);
    const bool c1 = lane & 2, c2 = lane & 4;
    const float u0 = untag(c1 ? v.z : v.x) + __shfl_xor_sync(0xffffffffu, untag(c1 ? v.x : v.z), 2);
    const float u1 = untag(c1 ? v.w : v.y) + __shfl_xor_sync(0xffffffffu, untag(c1 ? v.y : v.w), 2);
    float u = (c2 ? u1 : u0) + __shfl_xor_sync(0xffffffffu, c2 ? u0 : u1, 4);
    u += __shfl_xor_sync(0xffffffffu, u, 8);
    u += __shfl_xor_sync(0xffffffffu, u, 16);
    return u;
}

__device__ __forceinline__ unsigned kv_slot(int op) {
    return op < 8 ? SM_KV + op * CHUNK : (op < 12 ? SM_T + (op - 8) * TSLOT : SM_KV + (op - 12) * CHUNK);
}

__global__ void __launch_bounds__(NTHREADS, 1)
fused_decode_kernel(const __nv_bfloat16* __restrict__ wq, const __nv_bfloat16* __restrict__ kc,
                    const __nv_bfloat16* __restrict__ x, Scratch* __restrict__ sc,
                    const __nv_bfloat16* __restrict__ b1, const __nv_bfloat16* __restrict__ b2,
                    const __nv_bfloat16* __restrict__ vc, __nv_bfloat16* __restrict__ out,
                    const __grid_constant__ CUtensorMap w1map, const __grid_constant__ CUtensorMap w2map,
                    const __grid_constant__ CUtensorMap womap) {
    extern __shared__ __align__(1024) unsigned char smem[];
    const unsigned sb = (unsigned)__cvta_generic_to_shared(smem);
    const int b = blockIdx.x, tid = threadIdx.x, lane = tid & 31, warp = tid >> 5;
    const int g = lane >> 2, t = lane & 3;
    const bool att = b < NATT;
    const unsigned bar_full = sb + SM_BAR, bar_empty = bar_full + NOPS * 8;
    const int grp = b >> 3, r = b & 7;
    const int hid0 = att ? 32 * b : QC + 128 * (b - NATT);

    if (warp == 8) {
        PROF(lane == 0, 0);
        const unsigned tstart = gtime32();
        if (lane == 0) {
            for (int i = 0; i < NINIT; i++) mbar_init(bar_full + 8 * i, 1);
            asm volatile("fence.mbarrier_init.release.cluster;" ::: "memory");
        }
        if (att) {
            const size_t kvoff = ((size_t)grp * SK + (SK - WIN)) * DH * 2 + (size_t)r * CHUNK;
            const char* kp = reinterpret_cast<const char*>(kc) + kvoff;
            const char* vp = reinterpret_cast<const char*>(vc) + kvoff;
#pragma unroll 1
            for (int i = 0; i < NOPS; i++) {
                const int d = i < SWITCH_AB ? DEPTH_A : (i < OP_H ? DEPTH_B : (i < OP_W ? DEPTH_H : DEPTH_C));
                if (i == NINIT) {
                    __syncwarp();
                    bar_arrive(1, NTHREADS);
                    if (lane < 3) {
                        const CUtensorMap* m = lane == 0 ? &w1map : (lane == 1 ? &w2map : &womap);
                        asm volatile("prefetch.tensormap [%0];" ::"l"(m) : "memory");
                    }
                    bar_sync(9, 288);
                }
                if (lane == 0) {
                    if (PACE_PS && i >= NINIT) {
                        const int kib = 36 + (i < OP_H ? 16 * (i + 1) : (i < OP_W ? 256 + 12 * (i - OP_H + 1) : 292 + 18 * (i - OP_W + 1)));
                        const int due = kib * PACE_PS / 1000 - PACE_LEAD;
                        while ((int)(gtime32() - tstart) < due) { }
                    }
                    if (i >= d) { mbar_wait(bar_full + 8 * (i - d)); PROF(true, 32 + i - d); }
                    if (i >= 12) mbar_wait(bar_empty + 8 * (i < OP_W ? i - 12 : i - OP_W + 8));
                    const unsigned bar = bar_full + 8 * i;
                    if (i < OP_H) {
                        mbar_expect_tx(bar, CHUNK);
                        bulk_load(sb + kv_slot(i), (i < OP_V ? kp : vp) + (size_t)(i & 7) * 8 * CHUNK, CHUNK, bar);
                    } else if (i < OP_W) {
                        mbar_expect_tx(bar, HBOX);
                        tma_2d(sb + SM_KV + (i - 12) * CHUNK, &w1map, hid0, (i - OP_H) * 192, bar);
                    } else {
                        const int j = i - OP_W;
                        mbar_expect_tx(bar, TSLOT);
                        tma_2d(sb + SM_T + j * TSLOT, j < 2 ? &w2map : &womap, 0, (32 * b + (j & 1) * 16) * 9, bar);
                    }
                }
            }
            PROF(lane == 0, 2);
        } else {
            __syncwarp();
            bar_arrive(1, NTHREADS);
            bar_sync(9, 288);
#pragma unroll 1
            for (int i = 0; i < 20; i++) {
                if (i == 15) bar_sync(11, 288);
                if (lane == 0) {
                    const unsigned bar = bar_full + 8 * i;
                    if (i < 12) {
                        mbar_expect_tx(bar, HBOX);
                        tma_2d(sb + i * HBOX, &w1map, hid0 + 32 * (i / 3), (i % 3) * 192, bar);
                    } else {
                        mbar_expect_tx(bar, TSLOT);
                        tma_2d(sb + (i < 15 ? 12 * HBOX + (i - 12) * TSLOT : (i - 15) * TSLOT), &w2map, 0,
                               (hid0 + (i - 12) * 16) * 9, bar);
                    }
                }
                __syncwarp();
            }
        }
        return;
    }

    if (warp == 9) {
        const unsigned epoch = ld_rlx(sc->epoch);
        uint2 b1raw;
        asm volatile("ld.global.nc.v2.u32 {%0,%1}, [%2];" : "=r"(b1raw.x), "=r"(b1raw.y)
                     : "l"(b1 + hid0 + (att ? (lane & 7) : lane) * 4));
        unsigned short xr, b2r;
        {
            const int ci = (b < NFIN ? b : 0) * 8 + (lane & 7);
            asm volatile("ld.global.nc.u16 %0, [%1];" : "=h"(b2r) : "l"(b2 + ci));
            asm volatile("ld.global.nc.u16 %0, [%1];" : "=h"(xr) : "l"(x + ci));
        }
        unsigned xw[9];
        const unsigned* xp = reinterpret_cast<const unsigned*>(x);
#pragma unroll
        for (int i = 0; i < 9; i++) asm volatile("ld.global.nc.u32 %0, [%1];" : "=r"(xw[i]) : "l"(xp + 32 * i + lane));
        bar_arrive(8, 288);
        PROF(lane == 0, 16);
        PROFD(lane == 0, 18, xw[0]);
        PROFD(lane == 0, 19, xw[8]);
        const unsigned tag = epoch % 3u + 1u;
#pragma unroll 1
        for (int pass = 0; pass < 2; pass++) {
            layernorm18(xw);
            unsigned* dst = reinterpret_cast<unsigned*>(smem + SM_XN + pass * (SM_Y - SM_XN)) + lane;
#pragma unroll
            for (int i = 0; i < 9; i++) dst[32 * i] = xw[i];
            if (pass == 0) {
                *reinterpret_cast<uint2*>(smem + SM_B1 + lane * 8) = b1raw;
                if (lane == 0) *reinterpret_cast<volatile unsigned*>(smem + SM_TAG) = tag;
                __syncwarp();
                bar_arrive(1, NTHREADS);
                PROF(lane == 0, 17);
            }
        }
        const float xb = bf_lo(xr) + bf_lo(b2r);
        PROF(lane == 0, 1);
        bar_sync(5, 288);
        if (!att) return;
        {
            const unsigned* ox = sc->ox + (size_t)b * 256 + lane * 4;
            const unsigned* ml = sc->ml + grp * 64 + lane * 2;
            uint4 oa, ob;
            uint2 mlv;
            int it = 0;
            bool ok;
            do {
                oa = ld_rlx4(ox);
                ob = ld_rlx4(ox + 128);
                mlv = ld_rlx2(ml);
                const unsigned bad = (mlv.x ^ tag) | (mlv.y ^ tag) | (oa.x ^ tag) | (oa.y ^ tag) | (oa.z ^ tag) |
                                     (oa.w ^ tag) | (ob.x ^ tag) | (ob.y ^ tag) | (ob.z ^ tag) | (ob.w ^ tag);
                ok = __all_sync(0xffffffffu, (bad & 3u) == 0);
            } while (!ok && ++it < SPIN_LIMIT);
            const float mj = untag(mlv.x);
            float M = fmaxf(mj, __shfl_xor_sync(0xffffffffu, mj, 4));
            M = fmaxf(M, __shfl_xor_sync(0xffffffffu, M, 8));
            M = fmaxf(M, __shfl_xor_sync(0xffffffffu, M, 16));
            const float wj = exp2f((mj - M) * 1.4426950408889634f);
            float L = wj * untag(mlv.y);
            L += __shfl_xor_sync(0xffffffffu, L, 4);
            L += __shfl_xor_sync(0xffffffffu, L, 8);
            L += __shfl_xor_sync(0xffffffffu, L, 16);
            const float wn = wj / L;
            const int src = (lane >> 3) * 4 + (r >> 2);
            const float wa = __shfl_sync(0xffffffffu, wn, src), wb = __shfl_sync(0xffffffffu, wn, src + 16);
            const float a0 = fmaf(wa, untag(oa.x), wb * untag(ob.x)), a1 = fmaf(wa, untag(oa.y), wb * untag(ob.y));
            const float a2 = fmaf(wa, untag(oa.z), wb * untag(ob.z)), a3 = fmaf(wa, untag(oa.w), wb * untag(ob.w));
            const bool c1 = lane & 8, c2 = lane & 16;
            const float u0 = (c1 ? a2 : a0) + __shfl_xor_sync(0xffffffffu, c1 ? a0 : a2, 8);
            const float u1 = (c1 ? a3 : a1) + __shfl_xor_sync(0xffffffffu, c1 ? a1 : a3, 8);
            const float u = (c2 ? u1 : u0) + __shfl_xor_sync(0xffffffffu, c2 ? u0 : u1, 16);
            reinterpret_cast<__nv_bfloat16*>(smem + SM_HS)[32 + (lane & 7) * 4 + (c1 ? 2 : 0) + (c2 ? 1 : 0)] =
                __float2bfloat16_rn(u);
            __syncwarp();
            bar_arrive(7, 288);
        }
        PROF(lane == 0, 3);
        if (b < NFIN) {
            mbar_wait(bar_full + 8 * (NOPS - 1));
            PROF(lane == 0, 14);
            const float mine = gather_piece(sc->part + (size_t)b * NCTA * 8 + (256 + lane) * 4, lane < 8, tag, lane);
            bar_sync(12, 288);
            PROF(lane == 0, 4);
            const float* fr = reinterpret_cast<const float*>(smem + SM_HRED) + (lane & 7);
            float u = ((fr[0] + fr[8]) + (fr[16] + fr[24])) + ((fr[32] + fr[40]) + (fr[48] + fr[56])) + mine;
            const int col = 4 * (lane & 1) + (lane & 2) + ((lane >> 2) & 1);
            u += __shfl_sync(0xffffffffu, xb, col);
            if (lane < 8) out[b * 8 + col] = __float2bfloat16_rn(u);
            if (b == 0 && lane == 0) st_rlx(sc->epoch, epoch + 1);
            PROF(lane == 0, 5);
        }
        return;
    }

    uint4 wr[9];
    unsigned* const qx_dst = sc->qx + (size_t)b * 256 + tid;
    bar_sync(8, 288);
    if (att) {
        st_rlx(qx_dst, 0u);
        if (QDELAY > 0) {
            const long long c0 = clock64();
            while (clock64() - c0 < QDELAY) { }
        }
        const char* p = reinterpret_cast<const char*>(wq) + (size_t)(72 * r + warp) * (QC * 2) + grp * 512 + lane * 16;
#pragma unroll
        for (int i = 0; i < 9; i++) wr[i] = ldg_stream(p + (size_t)i * 8 * (QC * 2));
    }
    if (lane == 0) {
        for (int i = NINIT + warp; i < NOPS + 12; i += 8) mbar_init(bar_full + 8 * i, i < NOPS ? 1 : 4);
        asm volatile("fence.mbarrier_init.release.cluster;" ::: "memory");
    }
    __syncwarp();
    bar_arrive(9, 288);
    unsigned* const part_dst = sc->part + ((size_t)(2 * warp + (t & 1) + 16 * (t >> 1)) * NCTA + b) * 8 + g;
    unsigned* const ox_dst = sc->ox + ((size_t)(grp * 8 + warp) * 8 + r) * 32 + lane;
    float* const red = reinterpret_cast<float*>(smem + SM_RED);

    bar_sync(1, NTHREADS);
    const unsigned tag = *reinterpret_cast<volatile unsigned*>(smem + SM_TAG);
    PROF(tid == 0, 6);

    if (att) {
        {
            float acc[8];
#pragma unroll
            for (int j = 0; j < 8; j++) acc[j] = 0.f;
            const unsigned short* xs = reinterpret_cast<const unsigned short*>(smem + SM_XN) + 72 * r + warp;
#pragma unroll
            for (int i = 0; i < 9; i++) {
                const float a = bf_lo(xs[8 * i]);
                acc[0] = fmaf(a, bf_lo(wr[i].x), acc[0]); acc[1] = fmaf(a, bf_hi(wr[i].x), acc[1]);
                acc[2] = fmaf(a, bf_lo(wr[i].y), acc[2]); acc[3] = fmaf(a, bf_hi(wr[i].y), acc[3]);
                acc[4] = fmaf(a, bf_lo(wr[i].z), acc[4]); acc[5] = fmaf(a, bf_hi(wr[i].z), acc[5]);
                acc[6] = fmaf(a, bf_lo(wr[i].w), acc[6]); acc[7] = fmaf(a, bf_hi(wr[i].w), acc[7]);
            }
            *reinterpret_cast<float4*>(red + warp * 256 + lane * 4) = make_float4(acc[0], acc[1], acc[2], acc[3]);
            *reinterpret_cast<float4*>(red + warp * 256 + 128 + lane * 4) = make_float4(acc[4], acc[5], acc[6], acc[7]);
        }
        PROF(tid == 0, 7);
        bar_sync(2, 256);
        {
            const float* src = red + ((tid >> 2) & 1) * 128 + (tid >> 3) * 4 + (tid & 3);
            float s = 0.f;
#pragma unroll
            for (int w = 0; w < 8; w++) s += src[w * 256];
            st_rlx(qx_dst, tagf(s, tag));
            st_rlx(ox_dst, 0u);
            if (warp == 1 && lane < 8) st_rlx(sc->ml + b * 8 + lane, 0u);
            const unsigned* qsrc = sc->qx + (size_t)grp * 2048 + tid;
            unsigned v[8], bad;
            int it = 0;
            do {
                bad = 0;
#pragma unroll
                for (int j = 0; j < 8; j++) v[j] = ld_rlx(qsrc + j * 256);
#pragma unroll
                for (int j = 0; j < 8; j++) bad |= v[j] ^ tag;
            } while ((bad & 3u) != 0 && ++it < SPIN_LIMIT);
            s = 0.f;
#pragma unroll
            for (int j = 0; j < 8; j++) s += untag(v[j]);
            reinterpret_cast<__nv_bfloat16*>(smem + SM_QS)[tid] = __float2bfloat16_rn(s);
        }
        bar_sync(3, 256);
        PROF(tid == 0, 8);
    }
    st_rlx(part_dst, 0u);
    st_rlx(part_dst + 32 * NCTA * 8, 0u);
    if (warp < 4 && t < 2) st_rlx(part_dst + 64 * NCTA * 8, 0u);

    if (att) {
        uint4 qf[4];
#pragma unroll
        for (int j = 0; j < 4; j++)
            qf[j] = lds128(sb + SM_QS + (g & 1) * 256 + (t + 4 * (j ^ ((g >> 1) & 1))) * 16);

        const int tile = warp & 3, cpar = warp >> 2;
        const int hsel = t >> 1;
        unsigned s0 = 0, s1 = 0, s2 = 0, s3 = 0;
        float mx = -INFINITY;
#pragma unroll 1
        for (int c = cpar; c < NCH; c += 2) {
            mbar_wait(bar_full + 8 * c);
            const unsigned base = sb + SM_KV + c * CHUNK + tile * 4096 + g * 256 + t * 16;
            uint4 ka[4], kb[4];
#pragma unroll
            for (int j = 0; j < 4; j++) {
                ka[j] = lds128(base + (j ^ (g & 1)) * 64);
                kb[j] = lds128(base + (j ^ (g & 1)) * 64 + 2048);
            }
            float cc[4] = {0.f, 0.f, 0.f, 0.f}, cd[4] = {0.f, 0.f, 0.f, 0.f};
#pragma unroll
            for (int j = 0; j < 4; j++) {
                mma16816(cc, ka[j].x, kb[j].x, ka[j].y, kb[j].y, qf[j].x, qf[j].y);
                mma16816(cd, ka[j].z, kb[j].z, ka[j].w, kb[j].w, qf[j].z, qf[j].w);
            }
            __syncwarp();
            if (lane == 0) mbar_arrive(bar_empty + 8 * c);
            const float scale = 0.08838834764831845f;
            const unsigned raw = pack_bf(hsel ? cc[1] + cd[1] : cc[0] + cd[0], hsel ? cc[3] + cd[3] : cc[2] + cd[2]);
            s0 = s1; s1 = s2; s2 = s3;
            s3 = pack_bf(bf_lo(raw) * scale, bf_hi(raw) * scale);
            mx = fmaxf(mx, fmaxf(bf_lo(s3), bf_hi(s3)));
        }
        PROF(tid == 0, 9);
        mx = fmaxf(mx, __shfl_xor_sync(0xffffffffu, mx, 5));
        mx = fmaxf(mx, __shfl_xor_sync(0xffffffffu, mx, 8));
        mx = fmaxf(mx, __shfl_xor_sync(0xffffffffu, mx, 16));
        float* const wmax = reinterpret_cast<float*>(smem + SM_WMAX);
        float* const wsum = reinterpret_cast<float*>(smem + SM_WSUM);
        if ((lane & ~2) == 0) wmax[hsel * 8 + warp] = mx;
        bar_sync(4, 256);
        float M;
        {
            const float4 m0 = *reinterpret_cast<const float4*>(wmax + hsel * 8);
            const float4 m1 = *reinterpret_cast<const float4*>(wmax + hsel * 8 + 4);
            M = fmaxf(fmaxf(fmaxf(m0.x, m0.y), fmaxf(m0.z, m0.w)), fmaxf(fmaxf(m1.x, m1.y), fmaxf(m1.z, m1.w)));
        }
        float ls = 0.f;
        float oa[2][4][4];
#pragma unroll
        for (int H = 0; H < 2; H++)
#pragma unroll
            for (int e = 0; e < 4; e++) oa[H][e][0] = oa[H][e][1] = oa[H][e][2] = oa[H][e][3] = 0.f;
#pragma unroll 1
        for (int c = cpar; c < NCH; c += 2) {
            const float ea = exp2f((bf_lo(s0) - M) * 1.4426950408889634f);
            const float eb = exp2f((bf_hi(s0) - M) * 1.4426950408889634f);
            s0 = s1; s1 = s2; s2 = s3;
            ls += ea + eb;
            const unsigned pk = pack_bf(ea, eb);
            const unsigned u0 = __shfl_sync(0xffffffffu, pk, 8 * t + 2 * (g & 1));
            const unsigned u1 = __shfl_sync(0xffffffffu, pk, 8 * t + 5 + 2 * (g & 1));
            const bool live = t == (g >> 1);
            const unsigned pb0 = live ? u0 : 0u, pb1 = live ? u1 : 0u;
            mbar_wait(bar_full + 8 * (OP_V + c));
            const unsigned base = sb + kv_slot(OP_V + c) + tile * 4096 + t * 512 + (g ^ (2 * t)) * 16;
#pragma unroll
            for (int H = 0; H < 2; H++) {
                const uint4 v0 = lds128(base + H * 128), v1 = lds128(base + H * 128 + 2048);
                const uint4 v2 = lds128(base + H * 128 + 256), v3 = lds128(base + H * 128 + 2304);
#define PV_STEP(e, f)                                                                                   \
                mma16816(oa[H][e], __byte_perm(v0.f, v1.f, 0x5410), __byte_perm(v0.f, v1.f, 0x7632),  \
                         __byte_perm(v2.f, v3.f, 0x5410), __byte_perm(v2.f, v3.f, 0x7632), pb0, pb1);
                PV_STEP(0, x) PV_STEP(1, y) PV_STEP(2, z) PV_STEP(3, w)
#undef PV_STEP
            }
            __syncwarp();
            if (lane == 0 && c < 4) mbar_arrive(bar_empty + 8 * (8 + c));
        }
        PROF(tid == 0, 10);
        ls += __shfl_xor_sync(0xffffffffu, ls, 5);
        ls += __shfl_xor_sync(0xffffffffu, ls, 8);
        ls += __shfl_xor_sync(0xffffffffu, ls, 16);
        if ((lane & ~2) == 0) wsum[hsel * 8 + warp] = ls;
        {
            const bool t0 = t & 1, t1 = t & 2;
            float r1[4][4], r2[2][4];
#pragma unroll
            for (int e = 0; e < 4; e++)
#pragma unroll
                for (int k = 0; k < 4; k++) {
                    const float send = t0 ? oa[0][e][k] : oa[1][e][k], keep = t0 ? oa[1][e][k] : oa[0][e][k];
                    r1[e][k] = keep + __shfl_xor_sync(0xffffffffu, send, 9);
                }
#pragma unroll
            for (int e = 0; e < 2; e++)
#pragma unroll
                for (int k = 0; k < 4; k++) {
                    const float send = t1 ? r1[e][k] : r1[e + 2][k], keep = t1 ? r1[e + 2][k] : r1[e][k];
                    r2[e][k] = keep + __shfl_xor_sync(0xffffffffu, send, 18);
                }
            float* const dst = red + warp * 256 + (t & 1) * 64 + (g ^ (2 * t)) * 8 + (t >> 1) * 4;
            *reinterpret_cast<float4*>(dst) = make_float4(r2[0][0], r2[0][2], r2[1][0], r2[1][2]);
            *reinterpret_cast<float4*>(dst + 128) = make_float4(r2[0][1], r2[0][3], r2[1][1], r2[1][3]);
        }
        bar_sync(5, 288);
        float s = 0.f;
#pragma unroll
        for (int w = 0; w < 8; w++) s += red[w * 256 + tid];
        st_rlx(ox_dst, tagf(s, tag));
        if (warp == 1 && lane < 8) {
            float v = 0.f;
            const float* src = (lane & 1) ? wsum : wmax;
            if (lane < 4) {
                src += (lane >> 1) * 8;
                v = src[0];
#pragma unroll
                for (int w = 1; w < 8; w++) v = (lane & 1) ? v + src[w] : fmaxf(v, src[w]);
            }
            st_rlx(sc->ml + b * 8 + lane, tagf(v, tag));
        }
        PROF(tid == 0, 11);
    } else {
        bar_sync(5, 288);
    }

    const int krow = (lane & 7) + ((lane >> 4) & 1) * 8, khalf = (lane >> 3) & 1;
    float* const hred = reinterpret_cast<float*>(smem + SM_HRED);
    {
        const int nslab = att ? 1 : 4;
        const unsigned hbase = sb + (att ? 4 * CHUNK : 0) + krow * 64, hstride = att ? CHUNK : HBOX;
        const unsigned hbar = bar_full + 8 * (att ? OP_H : 0);
        const unsigned sw0 = (khalf ^ ((krow >> 1) & 3)) * 16;
#pragma unroll 1
        for (int sl = 0; sl < nslab; sl++) {
            float c0[4] = {0.f, 0.f, 0.f, 0.f}, c1[4] = {0.f, 0.f, 0.f, 0.f};
#pragma unroll 1
            for (int kk = warp; kk < 36; kk += 8) {
                const int j = kk / 12;
                const unsigned vb0 = lds32(sb + SM_Y + (kk * 8 + t) * 4), vb1 = lds32(sb + SM_Y + (kk * 8 + 4 + t) * 4);
                mbar_wait(hbar + 8 * (3 * sl + j));
                const unsigned base = hbase + sl * 3 * HBOX + j * hstride + (kk - 12 * j) * 1024;
                unsigned a0[4], a1[4];
                ldsm4t(a0, base + sw0);
                ldsm4t(a1, base + (sw0 ^ 32));
                mma16816(c0, a0[0], a0[1], a0[2], a0[3], vb0, vb1);
                mma16816(c1, a1[0], a1[1], a1[2], a1[3], vb0, vb1);
            }
            hred[(sl * 8 + warp) * 32 + 8 * t + g] = (t & 2) ? ((t & 1) ? c1[2] : c1[0]) : ((t & 1) ? c0[2] : c0[0]);
        }
        bar_sync(6, 256);
        if (!att) bar_arrive(11, 288);
        if (warp < nslab) {
            float s = 0.f;
#pragma unroll
            for (int w = 0; w < 8; w++) s += hred[(warp * 8 + w) * 32 + lane];
            const float bias = bf_lo(reinterpret_cast<const unsigned short*>(smem + SM_B1)[tid]);
            reinterpret_cast<__nv_bfloat16*>(smem + SM_HS)[tid] = __float2bfloat16_rn(gelu_tanh(bfr(bfr(s) + bias)));
        }
        bar_sync(10, 256);
    }
    PROF(tid == 0, 15);
    float acc5[5][4];
    unsigned woff[5];
#pragma unroll
    for (int i = 0; i < 5; i++) {
        acc5[i][0] = acc5[i][1] = acc5[i][2] = acc5[i][3] = 0.f;
        const int line = 9 * krow + (warp >> 2) + 2 * i;
        woff[i] = line * 128 + ((((warp & 3) * 2 + khalf) ^ (line & 7)) * 16);
    }
    {
        const int nks = att ? 4 : 8;
        const unsigned wbar = bar_full + 8 * (att ? OP_W : 12);
#pragma unroll 1
        for (int ks = 0; ks < nks; ks++) {
            if (att && ks == 2) { bar_sync(7, 288); PROF(tid == 0, 12); }
            const unsigned vb0 = lds32(sb + SM_HS + (ks * 8 + t) * 4), vb1 = lds32(sb + SM_HS + (ks * 8 + 4 + t) * 4);
            const unsigned base = sb + (att ? SM_T + ks * TSLOT : (ks < 3 ? 12 * HBOX + ks * TSLOT : (ks - 3) * TSLOT));
            mbar_wait(wbar + 8 * ks);
#pragma unroll
            for (int i = 0; i < 5; i++) {
                if (i < 4 || warp < 4) {
                    unsigned a[4];
                    ldsm4t(a, base + woff[i]);
                    mma16816(acc5[i], a[0], a[1], a[2], a[3], vb0, vb1);
                }
            }
        }
    }
    {
        const float v01 = (t & 2) ? ((t & 1) ? acc5[1][2] : acc5[1][0]) : ((t & 1) ? acc5[0][2] : acc5[0][0]);
        const float v23 = (t & 2) ? ((t & 1) ? acc5[3][2] : acc5[3][0]) : ((t & 1) ? acc5[2][2] : acc5[2][0]);
        const float v4 = (t & 1) ? acc5[4][2] : acc5[4][0];
        st_rlx(part_dst, tagf(v01, tag));
        st_rlx(part_dst + 32 * NCTA * 8, tagf(v23, tag));
        if (warp < 4 && t < 2) st_rlx(part_dst + 64 * NCTA * 8, tagf(v4, tag));
    }
    PROF(tid == 0, 13);
    if (b < NFIN) {
        const float u = gather_piece(sc->part + (size_t)b * NCTA * 8 + tid * 4, true, tag, lane);
        if (lane < 8) hred[warp * 8 + lane] = u;
        __syncwarp();
        bar_arrive(12, 288);
    }
}

}

extern "C" void kernel_launch(void* const* d_in, const int* in_sizes, int n_in, void* d_out, int out_size) {
    (void)in_sizes; (void)n_in; (void)out_size;
    typedef CUresult (*EncodeFn)(CUtensorMap*, CUtensorMapDataType, cuuint32_t, void*, const cuuint64_t*,
                                 const cuuint64_t*, const cuuint32_t*, const cuuint32_t*, CUtensorMapInterleave,
                                 CUtensorMapSwizzle, CUtensorMapL2promotion, CUtensorMapFloatOOBfill);
    static EncodeFn encode = nullptr;
    static CUtensorMap w1map, w2map, womap;
    static void* cached[3] = {nullptr, nullptr, nullptr};
    static Scratch* scratch = nullptr;
    if (!encode) {
        cudaGetSymbolAddress((void**)&scratch, g_scratch);
        cudaFuncSetAttribute(fused_decode_kernel, cudaFuncAttributeMaxDynamicSharedMemorySize, SM_TOTAL);
        void* fn = nullptr;
        cudaDriverEntryPointQueryResult qr;
        cudaGetDriverEntryPoint("cuTensorMapEncodeTiled", &fn, cudaEnableDefault, &qr);
        encode = (EncodeFn)fn;
    }
    if (cached[0] != d_in[6] || cached[1] != d_in[8] || cached[2] != d_in[4]) {
        const cuuint32_t estr[2] = {1, 1};
        {
            const cuuint64_t dims[2] = {(cuuint64_t)FF, (cuuint64_t)D_};
            const cuuint64_t strides[1] = {(cuuint64_t)FF * 2};
            const cuuint32_t box[2] = {32, 192};
            encode(&w1map, CU_TENSOR_MAP_DATA_TYPE_BFLOAT16, 2, d_in[6], dims, strides, box, estr,
                   CU_TENSOR_MAP_INTERLEAVE_NONE, CU_TENSOR_MAP_SWIZZLE_64B, CU_TENSOR_MAP_L2_PROMOTION_L2_128B,
                   CU_TENSOR_MAP_FLOAT_OOB_FILL_NONE);
        }
        for (int i = 0; i < 2; i++) {
            const cuuint64_t dims[2] = {64, (cuuint64_t)(i ? QC : FF) * 9};
            const cuuint64_t strides[1] = {128};
            const cuuint32_t box[2] = {64, 144};
            encode(i ? &womap : &w2map, CU_TENSOR_MAP_DATA_TYPE_BFLOAT16, 2, i ? d_in[4] : d_in[8], dims, strides, box,
                   estr, CU_TENSOR_MAP_INTERLEAVE_NONE, CU_TENSOR_MAP_SWIZZLE_128B,
                   CU_TENSOR_MAP_L2_PROMOTION_L2_128B, CU_TENSOR_MAP_FLOAT_OOB_FILL_NONE);
        }
        cached[0] = d_in[6]; cached[1] = d_in[8]; cached[2] = d_in[4];
    }
    fused_decode_kernel<<<NCTA, NTHREADS, SM_TOTAL>>>(
        (const __nv_bfloat16*)d_in[3], (const __nv_bfloat16*)d_in[1], (const __nv_bfloat16*)d_in[0], scratch,
        (const __nv_bfloat16*)d_in[7], (const __nv_bfloat16*)d_in[9], (const __nv_bfloat16*)d_in[2],
        (__nv_bfloat16*)d_out, w1map, w2map, womap);
}
```

```cpp
#include <cuda_runtime.h>
#include <cuda_bf16.h>
#include <cuda.h>
#include <stdint.h>

namespace {

constexpr int D_ = 576, SK = 16384, DH = 128, WIN = 4096, FF = 4608, QC = 4096;
constexpr int NATT = 128, NCTA = 132, NTHREADS = 320, NFIN = 72;
constexpr int CHUNK = 16384, NCH = 8;
constexpr int TSLOT = 16 * D_ * 2;
constexpr int HBOX = 192 * 64;
constexpr int WINDOW = 4, PACE_DNS_PER_KIB = 445  , PACE_LEAD_NS = 2500, PACE_STAGGER_NS = 40;
constexpr int OP_V = 8, OP_H = 16, OP_W = 19, OP_D = 23, NFULL = 25;
constexpr int NDIR = FF - QC;
constexpr int HX_POLL_NS = 9000;
constexpr int SPIN_LIMIT = 1 << 16;

constexpr int SM_KV = 0;
constexpr int SM_T = NCH * CHUNK;
constexpr int SM_RED = SM_T + 4 * TSLOT;
constexpr int SM_HRED = SM_RED + 8 * 256 * 4;
constexpr int SM_HD = SM_HRED + 4 * 8 * 32 * 4;
constexpr int SM_XN = SM_HD + NDIR * 2;
constexpr int SM_Y = SM_XN + D_ * 2;
constexpr int SM_B1 = SM_Y + D_ * 2;
constexpr int SM_QS = SM_B1 + 256;
constexpr int SM_HS = SM_QS + 512;
constexpr int SM_WMAX = SM_HS + 128;
constexpr int SM_WSUM = SM_WMAX + 64;
constexpr int SM_TAG = SM_WSUM + 64;
constexpr int SM_BAR = SM_TAG + 16;
constexpr int SM_TOTAL = SM_BAR + (NFULL + 12) * 8;
static_assert(SM_TOTAL <= 227 * 1024 && 12 * HBOX <= SM_RED && SM_BAR % 8 == 0, "shared memory map");

struct __align__(128) Scratch {
    unsigned epoch[32];
    unsigned qx[NATT * 256];
    unsigned ox[NATT * 8 * 32];
    unsigned ml[NATT * 8];
    unsigned hx[NDIR];
    unsigned part[NFIN * NATT * 8];
};
__device__ Scratch g_scratch;

__device__ __forceinline__ void mbar_init(unsigned bar, unsigned cnt) {
    asm volatile("mbarrier.init.shared::cta.b64 [%0], %1;" ::"r"(bar), "r"(cnt) : "memory");
}
__device__ __forceinline__ void mbar_expect_tx(unsigned bar, unsigned bytes) {
    asm volatile("mbarrier.arrive.expect_tx.shared::cta.b64 _, [%0], %1;" ::"r"(bar), "r"(bytes) : "memory");
}
__device__ __forceinline__ void mbar_arrive(unsigned bar) {
    asm volatile("mbarrier.arrive.shared::cta.b64 _, [%0];" ::"r"(bar) : "memory");
}
__device__ __forceinline__ void mbar_wait(unsigned bar) {
    unsigned ok;
    int it = 0;
    do {
        asm volatile(
            "{ .reg .pred p; mbarrier.try_wait.parity.shared::cta.b64 p, [%1], 0; selp.u32 %0, 1, 0, p; }"
            : "=r"(ok) : "r"(bar) : "memory");
    } while (!ok && ++it < SPIN_LIMIT);
}
__device__ __forceinline__ unsigned long long stream_policy() {
    unsigned long long pol;
    asm volatile("createpolicy.fractional.L2::evict_first.b64 %0, 1.0;" : "=l"(pol));
    return pol;
}
__device__ __forceinline__ void bulk_load(unsigned dst, const void* src, unsigned bytes, unsigned bar,
                                          unsigned long long pol) {
    asm volatile("cp.async.bulk.shared::cluster.global.mbarrier::complete_tx::bytes.L2::cache_hint [%0], [%1], %2, [%3], %4;"
                 ::"r"(dst), "l"(src), "r"(bytes), "r"(bar), "l"(pol) : "memory");
}
__device__ __forceinline__ uint4 ldg_stream(const void* p) {
    uint4 v;
    asm volatile("ld.global.nc.L1::no_allocate.v4.u32 {%0,%1,%2,%3}, [%4];"
                 : "=r"(v.x), "=r"(v.y), "=r"(v.z), "=r"(v.w) : "l"(p));
    return v;
}
__device__ __forceinline__ unsigned ld_rlx(const unsigned* p) {
    unsigned v;
    asm volatile("ld.relaxed.gpu.global.u32 %0, [%1];" : "=r"(v) : "l"(p) : "memory");
    return v;
}
__device__ __forceinline__ uint2 ld_rlx2(const unsigned* p) {
    uint2 v;
    asm volatile("ld.relaxed.gpu.global.v2.u32 {%0,%1}, [%2];" : "=r"(v.x), "=r"(v.y) : "l"(p) : "memory");
    return v;
}
__device__ __forceinline__ uint4 ld_rlx4(const unsigned* p) {
    uint4 v;
    asm volatile("ld.relaxed.gpu.global.v4.u32 {%0,%1,%2,%3}, [%4];"
                 : "=r"(v.x), "=r"(v.y), "=r"(v.z), "=r"(v.w) : "l"(p) : "memory");
    return v;
}
__device__ __forceinline__ void st_rlx(unsigned* p, unsigned v) {
    asm volatile("st.relaxed.gpu.global.u32 [%0], %1;" ::"l"(p), "r"(v) : "memory");
}
__device__ __forceinline__ void claim(unsigned* p) {
    st_rlx(p, 0u);
}
__device__ __forceinline__ uint4 lds128(unsigned a) {
    uint4 v;
    asm volatile("ld.shared.v4.u32 {%0,%1,%2,%3}, [%4];" : "=r"(v.x), "=r"(v.y), "=r"(v.z), "=r"(v.w) : "r"(a));
    return v;
}
__device__ __forceinline__ void bar_sync(int id, int n) { asm volatile("bar.sync %0, %1;" ::"r"(id), "r"(n) : "memory"); }
__device__ __forceinline__ void bar_arrive(int id, int n) { asm volatile("bar.arrive %0, %1;" ::"r"(id), "r"(n) : "memory"); }
__device__ __forceinline__ void mma16816(float (&c)[4], unsigned a0, unsigned a1, unsigned a2, unsigned a3,
                                         unsigned b0, unsigned b1) {
    asm volatile(
        "mma.sync.aligned.m16n8k16.row.col.f32.bf16.bf16.f32 {%0,%1,%2,%3}, {%4,%5,%6,%7}, {%8,%9}, {%0,%1,%2,%3};"
        : "+f"(c[0]), "+f"(c[1]), "+f"(c[2]), "+f"(c[3])
        : "r"(a0), "r"(a1), "r"(a2), "r"(a3), "r"(b0), "r"(b1));
}
__device__ __forceinline__ void ldsm4t(unsigned (&r)[4], unsigned a) {
    asm volatile("ldmatrix.sync.aligned.m8n8.x4.trans.shared.b16 {%0,%1,%2,%3}, [%4];"
                 : "=r"(r[0]), "=r"(r[1]), "=r"(r[2]), "=r"(r[3]) : "r"(a));
}
__device__ __forceinline__ float bfr(float v) { return __bfloat162float(__float2bfloat16_rn(v)); }
__device__ __forceinline__ float bf_lo(unsigned w) { return __uint_as_float(w << 16); }
__device__ __forceinline__ float bf_hi(unsigned w) { return __uint_as_float(w & 0xffff0000u); }
__device__ __forceinline__ unsigned pack_bf(float lo, float hi) {
    __nv_bfloat162 v = __floats2bfloat162_rn(lo, hi);
    return *reinterpret_cast<unsigned*>(&v);
}
__device__ __forceinline__ float warp_sum(float v) {
#pragma unroll
    for (int o = 16; o; o >>= 1) v += __shfl_xor_sync(0xffffffffu, v, o);
    return v;
}
__device__ __forceinline__ unsigned tagf(float v, unsigned tag) { return (__float_as_uint(v) & ~3u) | tag; }
__device__ __forceinline__ float untag(unsigned w) { return __uint_as_float(w & ~3u); }

__device__ __forceinline__ void tma_2d(unsigned dst, const CUtensorMap* map, int c0, int c1, unsigned bar,
                                       unsigned long long pol) {
    asm volatile(
        "cp.async.bulk.tensor.2d.shared::cluster.global.mbarrier::complete_tx::bytes.L2::cache_hint [%0], [%1, {%3, %4}], [%2], %5;"
        ::"r"(dst), "l"(map), "r"(bar), "r"(c0), "r"(c1), "l"(pol) : "memory");
}
__device__ __forceinline__ unsigned gtime32() {
    unsigned c;
    asm volatile("mov.u32 %0, %globaltimer_lo;" : "=r"(c));
    return c;
}
__device__ __forceinline__ void wait_until(unsigned tstart, int ns) {
    int it = 0;
    while ((int)(gtime32() - tstart) < ns && ++it < SPIN_LIMIT) { }
}
__device__ __forceinline__ unsigned lds32(unsigned a) {
    unsigned v;
    asm volatile("ld.shared.u32 %0, [%1];" : "=r"(v) : "r"(a));
    return v;
}

__device__ __forceinline__ void layernorm18(unsigned (&w)[9]) {
    float s0 = 0.f, s1 = 0.f, s2 = 0.f;
#pragma unroll
    for (int i = 0; i < 3; i++) {
        s0 += bf_lo(w[i]) + bf_hi(w[i]);
        s1 += bf_lo(w[i + 3]) + bf_hi(w[i + 3]);
        s2 += bf_lo(w[i + 6]) + bf_hi(w[i + 6]);
    }
    const float mean = warp_sum(s0 + s1 + s2) * (1.0f / D_);
    float q0 = 0.f, q1 = 0.f;
#pragma unroll
    for (int i = 0; i < 9; i++) {
        const float a = bf_lo(w[i]) - mean, c = bf_hi(w[i]) - mean;
        q0 = fmaf(a, a, q0);
        q1 = fmaf(c, c, q1);
    }
    const float var = bfr(warp_sum(q0 + q1) * (1.0f / D_));
    const float m = bfr(mean);
    float sq, rs;
    asm("sqrt.approx.f32 %0, %1;" : "=f"(sq) : "f"(bfr(var + 1e-5f)));
    asm("rcp.approx.f32 %0, %1;" : "=f"(rs) : "f"(bfr(sq)));
#pragma unroll
    for (int i = 0; i < 9; i++) {
        const unsigned d = pack_bf(bf_lo(w[i]) - m, bf_hi(w[i]) - m);
        w[i] = pack_bf(bf_lo(d) * rs, bf_hi(d) * rs);
    }
}
__device__ __forceinline__ float gelu_tanh(float x) {
    const float k0 = 0.7978845608028654f, k1 = 0.044715f;
    float inner = k0 * (x + k1 * x * x * x);
    return 0.5f * x * (1.0f + tanhf(inner));
}

__device__ __forceinline__ bool valid4(const uint4& v, unsigned tag) {
    return (((v.x ^ tag) | (v.y ^ tag) | (v.z ^ tag) | (v.w ^ tag)) & 3u) == 0;
}

__device__ __forceinline__ unsigned kv_slot(int op) {
    return op < 8 ? SM_KV + op * CHUNK : (op < 12 ? SM_T + (op - 8) * TSLOT : SM_KV + (op - 12) * CHUNK);
}

__global__ void __launch_bounds__(NTHREADS, 1)
fused_decode_kernel(const __nv_bfloat16* __restrict__ wq, const __nv_bfloat16* __restrict__ kc,
                    const __nv_bfloat16* __restrict__ x, Scratch* __restrict__ sc,
                    const __nv_bfloat16* __restrict__ b1, const __nv_bfloat16* __restrict__ b2,
                    const __nv_bfloat16* __restrict__ vc, __nv_bfloat16* __restrict__ out,
                    const __grid_constant__ CUtensorMap w1map, const __grid_constant__ CUtensorMap w2map,
                    const __grid_constant__ CUtensorMap womap, const __grid_constant__ CUtensorMap wdmap) {
    extern __shared__ __align__(1024) unsigned char smem[];
    const unsigned sb = (unsigned)__cvta_generic_to_shared(smem);
    const int tid = threadIdx.x < 64 ? 288 - (threadIdx.x & 32) + (threadIdx.x & 31) : threadIdx.x - 64;
    const int b = blockIdx.x, lane = tid & 31, warp = tid >> 5;
    const int g = lane >> 2, t = lane & 3;
    const bool att = b < NATT;
    const unsigned bar_full = sb + SM_BAR, bar_empty = bar_full + NFULL * 8;
    const int grp = b >> 3, r = b & 7;
    const bool fin = b < NFIN;
    const int hid0 = att ? 32 * b : QC + 128 * r;

    if (warp == 8) {
        const unsigned tstart = gtime32();
        const unsigned long long pol = stream_policy();
        if (lane == 0) {
            mbar_init(bar_full, 1);
            asm volatile("fence.mbarrier_init.release.cluster;" ::: "memory");
        }
        const size_t kvoff = ((size_t)grp * SK + (SK - WIN)) * DH * 2 + (size_t)r * CHUNK;
        const char* kp = reinterpret_cast<const char*>(kc) + kvoff;
        const char* vp = reinterpret_cast<const char*>(vc) + kvoff;
        const int nops = att ? (fin ? NFULL : OP_D) : 12;
#pragma unroll 1
        for (int i = 0; i < nops; i++) {
            if (i == (att ? 1 : 0)) {
                __syncwarp();
                bar_arrive(1, NTHREADS);
                if (lane < 4) {
                    const CUtensorMap* m = lane == 0 ? &w1map : (lane == 1 ? &w2map : (lane == 2 ? &womap : &wdmap));
                    asm volatile("prefetch.tensormap [%0];" ::"l"(m) : "memory");
                }
                bar_sync(9, 288);
            }
            if (lane == 0) {
                const unsigned bar = bar_full + 8 * i;
                if (att) {
                    const int kib = 36 + (i < OP_H ? 16 * (i + 1)
                                          : (i < OP_W ? 256 + 12 * (i - OP_H + 1)
                                             : (i < OP_D ? 292 + 18 * (i - OP_W + 1) : 366)));
                    const int due = kib * PACE_DNS_PER_KIB / 10 - PACE_LEAD_NS + grp * PACE_STAGGER_NS;
                    if (i >= 1) wait_until(tstart, due);
                    const int d = (i >= OP_H && i < OP_W) ? WINDOW - 1 : WINDOW;
                    if (i >= d && i < OP_D) mbar_wait(bar_full + 8 * (i - d));
                    if (i >= 12) mbar_wait(bar_empty + 8 * (i < OP_W ? i - 12 : (i < OP_D ? i - OP_W + 8 : 7)));
                }
                if (att && i < OP_H) {
                    mbar_expect_tx(bar, CHUNK);
                    bulk_load(sb + kv_slot(i), (i < OP_V ? kp : vp) + (size_t)(i & 7) * 8 * CHUNK, CHUNK, bar, pol);
                } else {
                    const CUtensorMap* m = &w1map;
                    unsigned dst, bytes = HBOX;
                    int c0, c1;
                    if (!att) {
                        dst = i * HBOX; c0 = hid0 + 32 * (i / 3); c1 = (i % 3) * 192;
                    } else if (i < OP_W) {
                        dst = (i - 12) * CHUNK; c0 = hid0; c1 = (i - OP_H) * 192;
                    } else if (i < OP_D) {
                        const int j = i - OP_W;
                        m = j < 2 ? &w2map : &womap; bytes = TSLOT; dst = SM_T + j * TSLOT;
                        c0 = 0; c1 = (32 * b + (j & 1) * 16) * 9;
                    } else {
                        m = &wdmap; bytes = 4096; dst = 7 * CHUNK + (i - OP_D) * 4096;
                        c0 = 8 * b; c1 = QC + 256 * (i - OP_D);
                    }
                    mbar_expect_tx(bar, bytes);
                    tma_2d(sb + dst, m, c0, c1, bar, pol);
                }
            }
        }
        return;
    }

    if (warp == 9) {
        const unsigned tstart = gtime32();
        const unsigned epoch = ld_rlx(sc->epoch);
        uint2 b1raw;
        asm volatile("ld.global.nc.v2.u32 {%0,%1}, [%2];" : "=r"(b1raw.x), "=r"(b1raw.y)
                     : "l"(b1 + hid0 + (att ? (lane & 7) : lane) * 4));
        unsigned short xr, b2r;
        {
            const int ci = (fin ? b : 0) * 8 + (lane & 7);
            asm volatile("ld.global.nc.u16 %0, [%1];" : "=h"(b2r) : "l"(b2 + ci));
            asm volatile("ld.global.nc.u16 %0, [%1];" : "=h"(xr) : "l"(x + ci));
        }
        unsigned xw[9];
        const unsigned* xp = reinterpret_cast<const unsigned*>(x);
#pragma unroll
        for (int i = 0; i < 9; i++) asm volatile("ld.global.nc.u32 %0, [%1];" : "=r"(xw[i]) : "l"(xp + 32 * i + lane));
        const unsigned tag = epoch % 3u + 1u;
        int npass = 2;
        asm volatile("" : "+r"(npass));
#pragma unroll 1
        for (int pass = 0; pass < npass; pass++) {
            layernorm18(xw);
            unsigned* dst = reinterpret_cast<unsigned*>(smem + SM_XN + pass * (SM_Y - SM_XN)) + lane;
#pragma unroll
            for (int i = 0; i < 9; i++) dst[32 * i] = xw[i];
            if (pass == 0) {
                *reinterpret_cast<uint2*>(smem + SM_B1 + lane * 8) = b1raw;
                if (lane == 0) *reinterpret_cast<volatile unsigned*>(smem + SM_TAG) = tag;
                __syncwarp();
                bar_arrive(1, NTHREADS);
            }
        }
        const float xb = bf_lo(xr) + bf_lo(b2r);
        if (fin) {
            wait_until(tstart, HX_POLL_NS);
            uint4 hv[4];
            int it = 0;
            bool ok;
            do {
#pragma unroll
                for (int i = 0; i < 4; i++) hv[i] = ld_rlx4(sc->hx + i * 128 + lane * 4);
                ok = valid4(hv[0], tag) && valid4(hv[1], tag) && valid4(hv[2], tag) && valid4(hv[3], tag);
            } while (!ok && ++it < SPIN_LIMIT);
#pragma unroll
            for (int i = 0; i < 4; i++)
                *reinterpret_cast<uint2*>(smem + SM_HD + i * 256 + lane * 8) =
                    make_uint2(__byte_perm(hv[i].x, hv[i].y, 0x7632), __byte_perm(hv[i].z, hv[i].w, 0x7632));
            __syncwarp();
        }
        bar_sync(5, 288);
        if (!att) return;
        {
            const unsigned* ox = sc->ox + (size_t)b * 256 + lane * 4;
            const unsigned* ml = sc->ml + grp * 64 + lane * 2;
            uint4 oa, ob;
            uint2 mlv;
            int it = 0;
            bool ok;
            do {
                oa = ld_rlx4(ox);
                ob = ld_rlx4(ox + 128);
                mlv = ld_rlx2(ml);
                ok = valid4(oa, tag) && valid4(ob, tag) && (((mlv.x ^ tag) | (mlv.y ^ tag)) & 3u) == 0;
                ok = __all_sync(0xffffffffu, ok);
            } while (!ok && ++it < SPIN_LIMIT);
            const float mj = untag(mlv.x);
            float M = fmaxf(mj, __shfl_xor_sync(0xffffffffu, mj, 4));
            M = fmaxf(M, __shfl_xor_sync(0xffffffffu, M, 8));
            M = fmaxf(M, __shfl_xor_sync(0xffffffffu, M, 16));
            const float wj = exp2f((mj - M) * 1.4426950408889634f);
            float L = wj * untag(mlv.y);
            L += __shfl_xor_sync(0xffffffffu, L, 4);
            L += __shfl_xor_sync(0xffffffffu, L, 8);
            L += __shfl_xor_sync(0xffffffffu, L, 16);
            const float wn = wj / L;
            const int src = (lane >> 3) * 4 + (r >> 2);
            const float wa = __shfl_sync(0xffffffffu, wn, src), wb = __shfl_sync(0xffffffffu, wn, src + 16);
            const float a0 = fmaf(wa, untag(oa.x), wb * untag(ob.x)), a1 = fmaf(wa, untag(oa.y), wb * untag(ob.y));
            const float a2 = fmaf(wa, untag(oa.z), wb * untag(ob.z)), a3 = fmaf(wa, untag(oa.w), wb * untag(ob.w));
            const bool c1 = lane & 8, c2 = lane & 16;
            const float u0 = (c1 ? a2 : a0) + __shfl_xor_sync(0xffffffffu, c1 ? a0 : a2, 8);
            const float u1 = (c1 ? a3 : a1) + __shfl_xor_sync(0xffffffffu, c1 ? a1 : a3, 8);
            const float u = (c2 ? u1 : u0) + __shfl_xor_sync(0xffffffffu, c2 ? u0 : u1, 16);
            reinterpret_cast<__nv_bfloat16*>(smem + SM_HS)[32 + (lane & 7) * 4 + (c1 ? 2 : 0) + (c2 ? 1 : 0)] =
                __float2bfloat16_rn(u);
            __syncwarp();
            bar_arrive(7, 288);
        }
        if (fin) {
            const int col = 4 * (lane & 1) + (lane & 2) + ((lane >> 2) & 1);
            const float mine = __shfl_sync(0xffffffffu, xb, col);
            __nv_bfloat16* op = out + b * 8 + col;
            asm volatile("" : "+l"(op));
            bar_sync(12, 288);
            const float* fr = reinterpret_cast<const float*>(smem + SM_HRED) + (lane & 7);
            const float u = (((mine + fr[0]) + (fr[8] + fr[16])) + (fr[24] + fr[32])) + ((fr[40] + fr[48]) + fr[56]);
            if (lane < 8) *op = __float2bfloat16_rn(u);
            if (b == 0 && lane == 0) st_rlx(sc->epoch, epoch + 1);
        }
        return;
    }

    uint4 wr[9];
    unsigned* const qx_dst = sc->qx + (size_t)b * 256 + tid;
    if (att) {
        const char* p = reinterpret_cast<const char*>(wq) + (size_t)(72 * r + warp) * (QC * 2) + grp * 512 + lane * 16;
#pragma unroll
        for (int i = 0; i < 9; i++) wr[i] = ldg_stream(p + (size_t)i * 8 * (QC * 2));
        claim(qx_dst);
    }
    if (lane == 0) {
#pragma unroll 1
        for (int i = 1 + warp; i < NFULL + 12; i += 8) mbar_init(bar_full + 8 * i, i < NFULL ? 1 : 4);
        asm volatile("fence.mbarrier_init.release.cluster;" ::: "memory");
    }
    __syncwarp();
    bar_arrive(9, 288);
    unsigned* const part_dst = sc->part + ((size_t)warp * NATT + b) * 32 + 8 * t + g;
    const int part3 = (16 + (warp >> 1) - warp) * NATT * 32 + 16 * (warp & 1);
    unsigned* const ox_dst = sc->ox + ((size_t)(grp * 8 + warp) * 8 + r) * 32 + lane;
    float* const red = reinterpret_cast<float*>(smem + SM_RED);

    bar_sync(1, NTHREADS);
    const unsigned tag = *reinterpret_cast<volatile unsigned*>(smem + SM_TAG);

    if (att) {
        {
            float acc[8];
#pragma unroll
            for (int j = 0; j < 8; j++) acc[j] = 0.f;
            const unsigned short* xs = reinterpret_cast<const unsigned short*>(smem + SM_XN) + 72 * r + warp;
#pragma unroll
            for (int i = 0; i < 9; i++) {
                const float a = bf_lo(xs[8 * i]);
                acc[0] = fmaf(a, bf_lo(wr[i].x), acc[0]); acc[1] = fmaf(a, bf_hi(wr[i].x), acc[1]);
                acc[2] = fmaf(a, bf_lo(wr[i].y), acc[2]); acc[3] = fmaf(a, bf_hi(wr[i].y), acc[3]);
                acc[4] = fmaf(a, bf_lo(wr[i].z), acc[4]); acc[5] = fmaf(a, bf_hi(wr[i].z), acc[5]);
                acc[6] = fmaf(a, bf_lo(wr[i].w), acc[6]); acc[7] = fmaf(a, bf_hi(wr[i].w), acc[7]);
            }
            *reinterpret_cast<float4*>(red + warp * 256 + lane * 4) = make_float4(acc[0], acc[1], acc[2], acc[3]);
            *reinterpret_cast<float4*>(red + warp * 256 + 128 + lane * 4) = make_float4(acc[4], acc[5], acc[6], acc[7]);
        }
        bar_sync(2, 256);
        {
            const float* src = red + ((tid >> 2) & 1) * 128 + (tid >> 3) * 4 + (tid & 3);
            float s = 0.f;
#pragma unroll
            for (int w = 0; w < 8; w++) s += src[w * 256];
            st_rlx(qx_dst, tagf(s, tag));
            const unsigned* qsrc = sc->qx + (size_t)grp * 2048 + tid;
            unsigned v[8], bad;
            int it = 0;
            do {
                bad = 0;
#pragma unroll
                for (int j = 0; j < 8; j++) v[j] = ld_rlx(qsrc + j * 256);
#pragma unroll
                for (int j = 0; j < 8; j++) bad |= v[j] ^ tag;
            } while ((bad & 3u) != 0 && ++it < SPIN_LIMIT);
            s = 0.f;
#pragma unroll
            for (int j = 0; j < 8; j++) s += untag(v[j]);
            reinterpret_cast<__nv_bfloat16*>(smem + SM_QS)[tid] = __float2bfloat16_rn(s);
        }
        bar_sync(3, 256);
    }

    if (att) {
        uint4 qf[4];
#pragma unroll
        for (int j = 0; j < 4; j++)
            qf[j] = lds128(sb + SM_QS + (g & 1) * 256 + (t + 4 * (j ^ ((g >> 1) & 1))) * 16);

        const int tile = warp & 3, cpar = warp >> 2;
        const int hsel = t >> 1;
        unsigned s0 = 0, s1 = 0, s2 = 0, s3 = 0;
        float mx = -INFINITY;
#pragma unroll 1
        for (int c = cpar; c < NCH; c += 2) {
            mbar_wait(bar_full + 8 * c);
            const unsigned base = sb + SM_KV + c * CHUNK + tile * 4096 + g * 256 + t * 16;
            uint4 ka[4], kb[4];
#pragma unroll
            for (int j = 0; j < 4; j++) {
                ka[j] = lds128(base + (j ^ (g & 1)) * 64);
                kb[j] = lds128(base + (j ^ (g & 1)) * 64 + 2048);
            }
            float cc[4] = {0.f, 0.f, 0.f, 0.f}, cd[4] = {0.f, 0.f, 0.f, 0.f};
#pragma unroll
            for (int j = 0; j < 4; j++) {
                mma16816(cc, ka[j].x, kb[j].x, ka[j].y, kb[j].y, qf[j].x, qf[j].y);
                mma16816(cd, ka[j].z, kb[j].z, ka[j].w, kb[j].w, qf[j].z, qf[j].w);
            }
            __syncwarp();
            if (lane == 0) mbar_arrive(bar_empty + 8 * c);
            const float scale = 0.08838834764831845f;
            const unsigned raw = pack_bf(hsel ? cc[1] + cd[1] : cc[0] + cd[0], hsel ? cc[3] + cd[3] : cc[2] + cd[2]);
            s0 = s1; s1 = s2; s2 = s3;
            s3 = pack_bf(bf_lo(raw) * scale, bf_hi(raw) * scale);
            mx = fmaxf(mx, fmaxf(bf_lo(s3), bf_hi(s3)));
        }
        mx = fmaxf(mx, __shfl_xor_sync(0xffffffffu, mx, 5));
        mx = fmaxf(mx, __shfl_xor_sync(0xffffffffu, mx, 8));
        mx = fmaxf(mx, __shfl_xor_sync(0xffffffffu, mx, 16));
        float* const wmax = reinterpret_cast<float*>(smem + SM_WMAX);
        float* const wsum = reinterpret_cast<float*>(smem + SM_WSUM);
        if ((lane & ~2) == 0) wmax[hsel * 8 + warp] = mx;
        claim(ox_dst);
        if (warp == 1 && lane < 8) claim(sc->ml + b * 8 + lane);
        bar_sync(4, 256);
        float M;
        {
            const float4 m0 = *reinterpret_cast<const float4*>(wmax + hsel * 8);
            const float4 m1 = *reinterpret_cast<const float4*>(wmax + hsel * 8 + 4);
            M = fmaxf(fmaxf(fmaxf(m0.x, m0.y), fmaxf(m0.z, m0.w)), fmaxf(fmaxf(m1.x, m1.y), fmaxf(m1.z, m1.w)));
        }
        float ls = 0.f;
        float oa[2][4][4];
#pragma unroll
        for (int H = 0; H < 2; H++)
#pragma unroll
            for (int e = 0; e < 4; e++) oa[H][e][0] = oa[H][e][1] = oa[H][e][2] = oa[H][e][3] = 0.f;
#pragma unroll 1
        for (int c = cpar; c < NCH; c += 2) {
            const float ea = exp2f((bf_lo(s0) - M) * 1.4426950408889634f);
            const float eb = exp2f((bf_hi(s0) - M) * 1.4426950408889634f);
            s0 = s1; s1 = s2; s2 = s3;
            ls += ea + eb;
            const unsigned pk = pack_bf(ea, eb);
            const unsigned u0 = __shfl_sync(0xffffffffu, pk, 8 * t + 2 * (g & 1));
            const unsigned u1 = __shfl_sync(0xffffffffu, pk, 8 * t + 5 + 2 * (g & 1));
            const bool live = t == (g >> 1);
            const unsigned pb0 = live ? u0 : 0u, pb1 = live ? u1 : 0u;
            mbar_wait(bar_full + 8 * (OP_V + c));
            const unsigned base = sb + kv_slot(OP_V + c) + tile * 4096 + t * 512 + (g ^ (2 * t)) * 16;
#pragma unroll
            for (int H = 0; H < 2; H++) {
                const uint4 v0 = lds128(base + H * 128), v1 = lds128(base + H * 128 + 2048);
                const uint4 v2 = lds128(base + H * 128 + 256), v3 = lds128(base + H * 128 + 2304);
#define PV_STEP(e, f)                                                                                   \
                mma16816(oa[H][e], __byte_perm(v0.f, v1.f, 0x5410), __byte_perm(v0.f, v1.f, 0x7632),  \
                         __byte_perm(v2.f, v3.f, 0x5410), __byte_perm(v2.f, v3.f, 0x7632), pb0, pb1);
                PV_STEP(0, x) PV_STEP(1, y) PV_STEP(2, z) PV_STEP(3, w)
#undef PV_STEP
            }
            __syncwarp();
            if (lane == 0 && c < 4) mbar_arrive(bar_empty + 8 * (8 + c));
        }
        ls += __shfl_xor_sync(0xffffffffu, ls, 5);
        ls += __shfl_xor_sync(0xffffffffu, ls, 8);
        ls += __shfl_xor_sync(0xffffffffu, ls, 16);
        if ((lane & ~2) == 0) wsum[hsel * 8 + warp] = ls;
        {
            const bool t0 = t & 1, t1 = t & 2;
            float r1[4][4], r2[2][4];
#pragma unroll
            for (int e = 0; e < 4; e++)
#pragma unroll
                for (int k = 0; k < 4; k++) {
                    const float send = t0 ? oa[0][e][k] : oa[1][e][k], keep = t0 ? oa[1][e][k] : oa[0][e][k];
                    r1[e][k] = keep + __shfl_xor_sync(0xffffffffu, send, 9);
                }
#pragma unroll
            for (int e = 0; e < 2; e++)
#pragma unroll
                for (int k = 0; k < 4; k++) {
                    const float send = t1 ? r1[e][k] : r1[e + 2][k], keep = t1 ? r1[e + 2][k] : r1[e][k];
                    r2[e][k] = keep + __shfl_xor_sync(0xffffffffu, send, 18);
                }
            float* const dst = red + warp * 256 + (t & 1) * 64 + (g ^ (2 * t)) * 8 + (t >> 1) * 4;
            *reinterpret_cast<float4*>(dst) = make_float4(r2[0][0], r2[0][2], r2[1][0], r2[1][2]);
            *reinterpret_cast<float4*>(dst + 128) = make_float4(r2[0][1], r2[0][3], r2[1][1], r2[1][3]);
        }
        bar_sync(5, 288);
        float s = 0.f;
#pragma unroll
        for (int w = 0; w < 8; w++) s += red[w * 256 + tid];
        st_rlx(ox_dst, tagf(s, tag));
        if (warp == 1 && lane < 8) {
            float v = 0.f;
            const float* src = (lane & 1) ? wsum : wmax;
            if (lane < 4) {
                src += (lane >> 1) * 8;
                v = src[0];
#pragma unroll
                for (int w = 1; w < 8; w++) v = (lane & 1) ? v + src[w] : fmaxf(v, src[w]);
            }
            st_rlx(sc->ml + b * 8 + lane, tagf(v, tag));
        }
        claim(part_dst);
        claim(part_dst + 8 * NATT * 32);
        if (warp < 4 && t < 2) claim(part_dst + part3);
    } else {
        bar_sync(5, 288);
    }

    const int krow = (lane & 7) + ((lane >> 4) & 1) * 8, khalf = (lane >> 3) & 1;
    float* const hred = reinterpret_cast<float*>(smem + SM_HRED);
    {
        const int nslab = att ? 1 : 4;
        const unsigned hbase = sb + (att ? 4 * CHUNK : 0) + krow * 64, hstride = att ? CHUNK : HBOX;
        const unsigned hbar = bar_full + 8 * (att ? OP_H : 0);
        const unsigned sw0 = (khalf ^ ((krow >> 1) & 3)) * 16;
#pragma unroll 1
        for (int sl = 0; sl < nslab; sl++) {
            float c0[4] = {0.f, 0.f, 0.f, 0.f}, c1[4] = {0.f, 0.f, 0.f, 0.f};
#pragma unroll 1
            for (int kk = warp; kk < 36; kk += 8) {
                const int j = kk / 12;
                const unsigned vb0 = lds32(sb + SM_Y + (kk * 8 + t) * 4), vb1 = lds32(sb + SM_Y + (kk * 8 + 4 + t) * 4);
                mbar_wait(hbar + 8 * (3 * sl + j));
                const unsigned base = hbase + sl * 3 * HBOX + j * hstride + (kk - 12 * j) * 1024;
                unsigned a0[4], a1[4];
                ldsm4t(a0, base + sw0);
                ldsm4t(a1, base + (sw0 ^ 32));
                mma16816(c0, a0[0], a0[1], a0[2], a0[3], vb0, vb1);
                mma16816(c1, a1[0], a1[1], a1[2], a1[3], vb0, vb1);
            }
            hred[(sl * 8 + warp) * 32 + 8 * t + g] = (t & 2) ? ((t & 1) ? c1[2] : c1[0]) : ((t & 1) ? c0[2] : c0[0]);
        }
        bar_sync(6, 256);
        if (warp < nslab) {
            float s = 0.f;
#pragma unroll
            for (int w = 0; w < 8; w++) s += hred[(warp * 8 + w) * 32 + lane];
            const float bias = bf_lo(reinterpret_cast<const unsigned short*>(smem + SM_B1)[tid]);
            const unsigned hv = pack_bf(gelu_tanh(bfr(bfr(s) + bias)), 0.f);
            if (att) reinterpret_cast<unsigned short*>(smem + SM_HS)[tid] = (unsigned short)hv;
            else st_rlx(sc->hx + 128 * r + tid, (hv << 16) | tag);
        }
        if (!att) return;
        bar_sync(10, 256);
    }
    float acc5[5][4];
    unsigned woff[5];
#pragma unroll
    for (int i = 0; i < 5; i++) {
        acc5[i][0] = acc5[i][1] = acc5[i][2] = acc5[i][3] = 0.f;
        const int tl = i == 4 ? 32 + (warp & 3) : 2 * warp + (i & 1) + 16 * (i >> 1);
        const int line = 9 * krow + (tl >> 2);
        woff[i] = line * 128 + ((((tl & 3) * 2 + khalf) ^ (line & 7)) * 16);
    }
    unsigned long long pdst = reinterpret_cast<unsigned long long>(part_dst);
    unsigned long long psrc = reinterpret_cast<unsigned long long>(
        sc->part + ((size_t)(b >> 2) * NATT + (tid >> 1)) * 32 + (b & 3) * 8 + (tid & 1) * 4);
    asm volatile("" : "+l"(pdst), "+l"(psrc));
    {
#pragma unroll 1
        for (int ks = 0; ks < 4; ks++) {
            if (ks == 2) bar_sync(7, 288);
            const unsigned vb0 = lds32(sb + SM_HS + (ks * 8 + t) * 4), vb1 = lds32(sb + SM_HS + (ks * 8 + 4 + t) * 4);
            const unsigned base = sb + SM_T + ks * TSLOT;
            mbar_wait(bar_full + 8 * (OP_W + ks));
            unsigned a[5][4];
#pragma unroll
            for (int i = 0; i < 5; i++) ldsm4t(a[i], base + woff[i]);
#pragma unroll
            for (int i = 0; i < 5; i++) mma16816(acc5[i], a[i][0], a[i][1], a[i][2], a[i][3], vb0, vb1);
        }
    }
    {
        const float v01 = (t & 2) ? ((t & 1) ? acc5[1][2] : acc5[1][0]) : ((t & 1) ? acc5[0][2] : acc5[0][0]);
        const float v23 = (t & 2) ? ((t & 1) ? acc5[3][2] : acc5[3][0]) : ((t & 1) ? acc5[2][2] : acc5[2][0]);
        const float v4 = (t & 1) ? acc5[4][2] : acc5[4][0];
        unsigned* const pd = reinterpret_cast<unsigned*>(pdst);
        st_rlx(pd, tagf(v01, tag));
        st_rlx(pd + 8 * NATT * 32, tagf(v23, tag));
        if (warp < 4 && t < 2) st_rlx(pd + part3, tagf(v4, tag));
    }
    if (fin) {
        float dc[4] = {0.f, 0.f, 0.f, 0.f};
#pragma unroll 1
        for (int j = 0; j < 2; j++) {
            const unsigned hvec = sb + SM_HD + j * 512 + warp * 64 + t * 4;
            const unsigned h0 = lds32(hvec), h1 = lds32(hvec + 16), h2 = lds32(hvec + 32), h3 = lds32(hvec + 48);
            mbar_wait(bar_full + 8 * (OP_D + j));
            unsigned bm[4];
            ldsm4t(bm, sb + 7 * CHUNK + j * 4096 + warp * 512 + lane * 16);
            mma16816(dc, h0, h0, h1, h1, bm[0], bm[1]);
            mma16816(dc, h2, h2, h3, h3, bm[2], bm[3]);
        }
        const int col = 4 * (lane & 1) + (lane & 2) + ((lane >> 2) & 1);
        const float d0 = __shfl_sync(0xffffffffu, dc[0], col >> 1), d1 = __shfl_sync(0xffffffffu, dc[1], col >> 1);
        uint4 v;
        bool need = true;
        int it = 0;
        do {
            if (need) {
                v = ld_rlx4(reinterpret_cast<const unsigned*>(psrc));
                need = !valid4(v, tag);
            }
        } while (__any_sync(0xffffffffu, need) && ++it < SPIN_LIMIT);
        const bool c1 = lane & 2, c2 = lane & 4;
        const float u0 = untag(c1 ? v.z : v.x) + __shfl_xor_sync(0xffffffffu, untag(c1 ? v.x : v.z), 2);
        const float u1 = untag(c1 ? v.w : v.y) + __shfl_xor_sync(0xffffffffu, untag(c1 ? v.y : v.w), 2);
        float u = (c2 ? u1 : u0) + __shfl_xor_sync(0xffffffffu, c2 ? u0 : u1, 4);
        u += __shfl_xor_sync(0xffffffffu, u, 8);
        u += __shfl_xor_sync(0xffffffffu, u, 16);
        if (lane < 8) hred[warp * 8 + lane] = u + ((col & 1) ? d1 : d0);
        __syncwarp();
        bar_arrive(12, 288);
    }
}

__device__ float g_fb[2 * D_ + 2 * QC + FF];

__global__ void fb_ln(const __nv_bfloat16* x) {
    unsigned w[9];
    for (int i = 0; i < 9; i++) w[i] = reinterpret_cast<const unsigned*>(x)[32 * i + threadIdx.x];
    for (int pass = 0; pass < 2; pass++) {
        layernorm18(w);
        for (int i = 0; i < 9; i++) {
            g_fb[pass * D_ + 64 * i + 2 * threadIdx.x] = bf_lo(w[i]);
            g_fb[pass * D_ + 64 * i + 2 * threadIdx.x + 1] = bf_hi(w[i]);
        }
    }
}
__global__ void fb_proj(const __nv_bfloat16* wq, const __nv_bfloat16* w1, const __nv_bfloat16* b1) {
    const int c = blockIdx.x * blockDim.x + threadIdx.x;
    const bool isq = c < QC;
    const int cc = isq ? c : c - QC, n = isq ? QC : FF;
    const __nv_bfloat16* w = isq ? wq : w1;
    float s = 0.f;
    for (int k = 0; k < D_; k++) s = fmaf(g_fb[(isq ? 0 : D_) + k], __bfloat162float(w[(size_t)k * n + cc]), s);
    if (isq) g_fb[2 * D_ + cc] = bfr(s);
    else g_fb[2 * D_ + 2 * QC + cc] = bfr(gelu_tanh(bfr(bfr(s) + __bfloat162float(b1[cc]))));
}
__global__ void fb_attn(const __nv_bfloat16* kc, const __nv_bfloat16* vc) {
    __shared__ float sc[WIN], rd[DH];
    const int h = blockIdx.x, tid = threadIdx.x;
    const size_t base = ((size_t)(h >> 1) * SK + (SK - WIN)) * DH;
    float m = -INFINITY;
    for (int j = tid; j < WIN; j += DH) {
        float s = 0.f;
        for (int d = 0; d < DH; d++)
            s = fmaf(g_fb[2 * D_ + h * DH + d], __bfloat162float(kc[base + (size_t)j * DH + d]), s);
        sc[j] = bfr(bfr(s) * 0.08838834764831845f);
        m = fmaxf(m, sc[j]);
    }
    rd[tid] = m;
    __syncthreads();
    for (int i = 0; i < DH; i++) m = fmaxf(m, rd[i]);
    __syncthreads();
    float l = 0.f;
    for (int j = tid; j < WIN; j += DH) { sc[j] = expf(sc[j] - m); l += sc[j]; }
    rd[tid] = l;
    __syncthreads();
    l = 0.f;
    for (int i = 0; i < DH; i++) l += rd[i];
    float o = 0.f;
    for (int j = 0; j < WIN; j++) o = fmaf(bfr(sc[j] / l), __bfloat162float(vc[base + (size_t)j * DH + tid]), o);
    g_fb[2 * D_ + QC + h * DH + tid] = bfr(o);
}
__global__ void fb_out(const __nv_bfloat16* x, const __nv_bfloat16* wo, const __nv_bfloat16* w2,
                       const __nv_bfloat16* b2, __nv_bfloat16* out) {
    const int c = blockIdx.x * blockDim.x + threadIdx.x;
    float a = 0.f, m = 0.f;
    for (int k = 0; k < QC; k++) a = fmaf(g_fb[2 * D_ + QC + k], __bfloat162float(wo[(size_t)k * D_ + c]), a);
    for (int k = 0; k < FF; k++) m = fmaf(g_fb[2 * D_ + 2 * QC + k], __bfloat162float(w2[(size_t)k * D_ + c]), m);
    out[c] = __float2bfloat16_rn(bfr(__bfloat162float(x[c]) + bfr(a)) + bfr(bfr(m) + __bfloat162float(b2[c])));
}

}

extern "C" void kernel_launch(void* const* d_in, const int* in_sizes, int n_in, void* d_out, int out_size) {
    (void)in_sizes; (void)n_in; (void)out_size;
    typedef CUresult (*EncodeFn)(CUtensorMap*, CUtensorMapDataType, cuuint32_t, void*, const cuuint64_t*,
                                 const cuuint64_t*, const cuuint32_t*, const cuuint32_t*, CUtensorMapInterleave,
                                 CUtensorMapSwizzle, CUtensorMapL2promotion, CUtensorMapFloatOOBfill);
    typedef const __nv_bfloat16* bp;
    static int mode = 0;
    static EncodeFn encode = nullptr;
    static CUtensorMap w1map, w2map, womap, wdmap;
    static void* cached[3] = {nullptr, nullptr, nullptr};
    static Scratch* scratch = nullptr;
    if (mode == 0) {
        int dev = 0, sms = 0, occ = 0;
        void* fn = nullptr;
        cudaDriverEntryPointQueryResult qr;
        cudaGetDevice(&dev);
        cudaDeviceGetAttribute(&sms, cudaDevAttrMultiProcessorCount, dev);
        cudaGetSymbolAddress((void**)&scratch, g_scratch);
        cudaFuncSetAttribute(fused_decode_kernel, cudaFuncAttributeMaxDynamicSharedMemorySize, SM_TOTAL);
        cudaOccupancyMaxActiveBlocksPerMultiprocessor(&occ, fused_decode_kernel, NTHREADS, SM_TOTAL);
        cudaGetDriverEntryPoint("cuTensorMapEncodeTiled", &fn, cudaEnableDefault, &qr);
        encode = (EncodeFn)fn;
        mode = (encode && scratch && sms * occ >= NCTA) ? 1 : 2;
        (void)cudaGetLastError();
    }
    if (mode == 1 && (cached[0] != d_in[6] || cached[1] != d_in[8] || cached[2] != d_in[4])) {
        const cuuint32_t estr[2] = {1, 1};
        CUresult rc;
        {
            const cuuint64_t dims[2] = {(cuuint64_t)FF, (cuuint64_t)D_};
            const cuuint64_t strides[1] = {(cuuint64_t)FF * 2};
            const cuuint32_t box[2] = {32, 192};
            rc = encode(&w1map, CU_TENSOR_MAP_DATA_TYPE_BFLOAT16, 2, d_in[6], dims, strides, box, estr,
                        CU_TENSOR_MAP_INTERLEAVE_NONE, CU_TENSOR_MAP_SWIZZLE_64B, CU_TENSOR_MAP_L2_PROMOTION_L2_128B,
                        CU_TENSOR_MAP_FLOAT_OOB_FILL_NONE);
        }
        if (rc == CUDA_SUCCESS) {
            const cuuint64_t dims[2] = {(cuuint64_t)D_, (cuuint64_t)FF};
            const cuuint64_t strides[1] = {(cuuint64_t)D_ * 2};
            const cuuint32_t box[2] = {8, 256};
            rc = encode(&wdmap, CU_TENSOR_MAP_DATA_TYPE_BFLOAT16, 2, d_in[8], dims, strides, box, estr,
                        CU_TENSOR_MAP_INTERLEAVE_NONE, CU_TENSOR_MAP_SWIZZLE_NONE, CU_TENSOR_MAP_L2_PROMOTION_L2_128B,
                        CU_TENSOR_MAP_FLOAT_OOB_FILL_NONE);
        }
        for (int i = 0; i < 2 && rc == CUDA_SUCCESS; i++) {
            const cuuint64_t dims[2] = {64, (cuuint64_t)(i ? QC : FF) * 9};
            const cuuint64_t strides[1] = {128};
            const cuuint32_t box[2] = {64, 144};
            rc = encode(i ? &womap : &w2map, CU_TENSOR_MAP_DATA_TYPE_BFLOAT16, 2, i ? d_in[4] : d_in[8], dims, strides,
                        box, estr, CU_TENSOR_MAP_INTERLEAVE_NONE, CU_TENSOR_MAP_SWIZZLE_128B,
                        CU_TENSOR_MAP_L2_PROMOTION_L2_128B, CU_TENSOR_MAP_FLOAT_OOB_FILL_NONE);
        }
        if (rc != CUDA_SUCCESS) mode = 2;
        cached[0] = d_in[6]; cached[1] = d_in[8]; cached[2] = d_in[4];
    }
    if (mode == 1) {
        fused_decode_kernel<<<NCTA, NTHREADS, SM_TOTAL>>>((bp)d_in[3], (bp)d_in[1], (bp)d_in[0], scratch, (bp)d_in[7],
                                                          (bp)d_in[9], (bp)d_in[2], (__nv_bfloat16*)d_out, w1map,
                                                          w2map, womap, wdmap);
    } else {
        fb_ln<<<1, 32>>>((bp)d_in[0]);
        fb_proj<<<(QC + FF) / 128, 128>>>((bp)d_in[3], (bp)d_in[6], (bp)d_in[7]);
        fb_attn<<<32, DH>>>((bp)d_in[1], (bp)d_in[2]);
        fb_out<<<D_ / 32, 32>>>((bp)d_in[0], (bp)d_in[4], (bp)d_in[8], (bp)d_in[9], (__nv_bfloat16*)d_out);
    }
}
```
